```python
import torch

def _softmax(x, axis=-1):
    return torch.softmax(x, dim=axis)
def _gelu(x):
    return torch.nn.functional.gelu(x, approximate="tanh")
def _silu(x):
    return torch.nn.functional.silu(x)
def _sigmoid(x):
    return torch.sigmoid(x)
def _layernorm(x, axis=-1, eps=1e-5):
    m = x.mean(dim=axis, keepdim=True)
    v = x.var(dim=axis, keepdim=True, unbiased=False)
    return (x - m) / torch.sqrt(v + eps)
def _scatter_add(tgt, idx, src, axis=0):
    return tgt.clone().index_add_(axis, idx, src)
def _segment_sum(src, seg, n):
    out = torch.zeros((n,) + src.shape[1:], dtype=src.dtype)
    return out.index_add_(0, seg, src)
def _pad(x, pw):
    flat = tuple(v for pair in reversed(pw) for v in pair)
    return torch.nn.functional.pad(x, flat)

kernel_name = 'recurrent_scan__linear_kernel_hedgehog__dense_activation_silu__prompt'

def setup_inputs():

    _w = (lambda a: (lambda t: t.to(torch.bfloat16) if t.is_floating_point() else t)(torch.as_tensor(a)))
    def _A_setup():
        B, S, D, H = 1, 2048, 640, 32
        Dh = D // H
        return {
            "x": _w((lambda *s: torch.randn(*s, dtype=torch.bfloat16) * 0.05)(B, S, D)),
            "wqkv": _w((lambda *s: torch.randn(*s, dtype=torch.bfloat16) * 0.4)(D, 3 * D)),
            "w_phi": _w((lambda *s: torch.randn(*s, dtype=torch.bfloat16) * 0.4)(H, Dh, Dh) * (Dh ** -0.5)),
            "wo": _w((lambda *s: torch.randn(*s, dtype=torch.bfloat16) * 0.2)(D, D)),
        }
    _A_in = _A_setup()

    def _B_setup():
        B, S, D, F = 1, 2048, 640, 1536
        return {
            "x": _w((lambda *s: torch.randn(*s, dtype=torch.bfloat16) * 0.05)(B, S, D)),
            "w1": _w((lambda *s: torch.randn(*s, dtype=torch.bfloat16) * 0.4)(D, F) * (D ** -0.5)),
            "w2": _w((lambda *s: torch.randn(*s, dtype=torch.bfloat16) * 0.1)(F, D) * (F ** -0.5)),
        }
    _B_in = _B_setup()

    return {
        "A_x": _A_in["x"],
        "A_wqkv": _A_in["wqkv"],
        "A_w_phi": _A_in["w_phi"],
        "A_wo": _A_in["wo"],
        "B_x": _B_in["x"],
        "B_w1": _B_in["w1"],
        "B_w2": _B_in["w2"],
    }

def reference(A_x, A_wqkv, A_w_phi, A_wo, B_x, B_w1, B_w2):
    def _A_ref(x, wqkv, w_phi, wo):
        B, S, D = x.shape
        H = 32; Dh = D // H
        qkv = (lambda x, *d: x.permute(*d))((x @ wqkv).reshape(B, S, 3, H, Dh), 2, 0, 3, 1, 4)
        q, k, v = qkv[0], qkv[1], qkv[2]
        pq = torch.einsum("bhsd,hdf->bhsf", q, w_phi)
        pk = torch.einsum("bhsd,hdf->bhsf", k, w_phi)
        phi_q = torch.concatenate([_softmax(pq, axis=-1), _softmax(-pq, axis=-1)], axis=-1)
        phi_k = torch.concatenate([_softmax(pk, axis=-1), _softmax(-pk, axis=-1)], axis=-1)
        kv = torch.einsum("bhsf,bhsd->bhfd", phi_k, v)
        z  = torch.einsum("bhsf->bhf", phi_k)
        num = torch.einsum("bhqf,bhfd->bhqd", phi_q, kv)
        den = torch.einsum("bhqf,bhf->bhq", phi_q, z)[..., None] + 1e-6
        o = num / den
        return (lambda x, *d: x.permute(*d))(o, 0, 2, 1, 3).reshape(B, S, D) @ wo

    def _B_ref(x, w1, w2):
        h = torch.einsum("bsd,df->bsf", x, w1)
        h = _silu(h)
        out = torch.einsum("bsf,fd->bsd", h, w2)
        return out

    x = A_x
    xn = _layernorm(x, axis=-1)
    s = _A_ref(xn, A_wqkv, A_w_phi, A_wo)
    g = _silu(_B_ref(xn, B_w1, B_w2))
    return x + s * g
```

```cpp
#include <cuda_runtime.h>
#include <cuda_bf16.h>
#include <cuda.h>
#include <stdint.h>

namespace {

constexpr int S_LEN = 2048, DM = 640, FF = 1536;
constexpr int NCTA = 128;
constexpr int NTHREADS = 384;

constexpr int NSLOT = 8;
constexpr int SLOT_BYTES = 20480;
constexpr int OFF_RING = 0;
constexpr int CH = 1056;
constexpr int OFF_W = NSLOT * SLOT_BYTES;
constexpr int W_BYTES = 22528;
constexpr int OFF_KVB = OFF_W + 2 * W_BYTES;
constexpr int KVB_HEAD = 2304;
constexpr int OFF_BAR = OFF_KVB + 15360;
constexpr int SMEM_USED = OFF_BAR + 1024;
constexpr int SMEM_BYTES = SMEM_USED + 1024;
static_assert(OFF_KVB % 128 == 0, "align");
static_assert(SMEM_BYTES <= 232448, "smem");

constexpr int B_FULL = 0, B_EMPTY = 8, B_FOLD = 16, B_STGFULL = 17, B_STGFREE = 19, B_VFREE = 21, B_KVB = 22, B_KVRAW = 23, B_EPOCH = 24, B_XRES = 25, B_FOLDDONE = 27, B_XD = 28;
constexpr int KV_FLOATS = 4 * 40 * 24;

struct Counters {
  unsigned epoch;
  unsigned pad0[31];
  unsigned fold[24 * 8];
  unsigned kv[8 * 8];
};
struct RowBlk {
  unsigned h[3 * 8];
  unsigned o[8];
  unsigned pad[224];
  uint4 xch[4 * 2 * 1280];
};
struct Scratch {
  Counters cnt;
  alignas(128) float kv[2][8 * KV_FLOATS];
  alignas(128) __nv_bfloat16 wp[1920 * DM];
  alignas(128) __nv_bfloat16 o[S_LEN * DM];
  alignas(128) __nv_bfloat16 h[S_LEN * FF];
  alignas(1024) RowBlk rb[16];
};
__device__ Scratch g_scr;

struct Maps {
  CUtensorMap x, raw, w1, wp, h_st, h_ld, o_st, o_ld, w2, wo, out_st, xres;
};

__device__ __forceinline__ uint32_t smem_u32(const void* p) { return (uint32_t)__cvta_generic_to_shared(p); }
__device__ __forceinline__ void mbar_init(uint32_t bar, int cnt) { asm volatile("mbarrier.init.shared::cta.b64 [%0], %1;" ::"r"(bar), "r"(cnt) : "memory"); }
__device__ __forceinline__ void mbar_expect_tx(uint32_t bar, uint32_t bytes) { asm volatile("mbarrier.arrive.expect_tx.shared::cta.b64 _, [%0], %1;" ::"r"(bar), "r"(bytes) : "memory"); }
__device__ __forceinline__ void mbar_arrive(uint32_t bar) { asm volatile("mbarrier.arrive.shared::cta.b64 _, [%0];" ::"r"(bar) : "memory"); }
__device__ __forceinline__ bool mbar_try(uint32_t bar, uint32_t parity) {
  uint32_t done;
  asm volatile("{\n.reg .pred p;\nmbarrier.try_wait.parity.shared::cta.b64 p, [%1], %2;\nselp.u32 %0, 1, 0, p;\n}" : "=r"(done) : "r"(bar), "r"(parity) : "memory");
  return done != 0;
}
__device__ __forceinline__ void mbar_wait(uint32_t bars, uint32_t idx, uint32_t parity) {
  const uint32_t bar = bars + 8 * idx;
  if (mbar_try(bar, parity)) return;
  uint32_t n = 0;
#pragma unroll 1
  while (!mbar_try(bar, parity)) {
    __nanosleep(100);
    if (++n > 0x200000u) break;
  }
}
__device__ __forceinline__ void mbar_wait_lazy(uint32_t bars, uint32_t idx, uint32_t parity) {
  const uint32_t bar = bars + 8 * idx;
  uint32_t n = 0;
#pragma unroll 1
  while (!mbar_try(bar, parity)) {
    __nanosleep(100);
    if (++n > 0x200000u) break;
  }
}
__device__ __forceinline__ unsigned ld_acquire(const unsigned* p) { unsigned v; asm volatile("ld.acquire.gpu.global.u32 %0, [%1];" : "=r"(v) : "l"(p) : "memory"); return v; }
__device__ __forceinline__ void red_release(unsigned* p, unsigned v) { asm volatile("red.release.gpu.global.add.u32 [%0], %1;" ::"l"(p), "r"(v) : "memory"); }
__device__ __forceinline__ void wait_counter(uint32_t, const unsigned* p, unsigned target) {
  uint32_t n = 0;
#pragma unroll 1
  while ((int)(ld_acquire(p) - target) < 0) {
    __nanosleep(100);
    if (++n > 0x200000u) break;
  }
}
__device__ __forceinline__ void fence_async_smem() { asm volatile("fence.proxy.async.shared::cta;" ::: "memory"); }
__device__ __forceinline__ void fence_async_global() { asm volatile("fence.proxy.async.global;" ::: "memory"); }
__device__ __forceinline__ void tma_2d(uint32_t dst, const CUtensorMap* m, uint32_t bar, int c0, int c1) {
  asm volatile("cp.async.bulk.tensor.2d.shared::cluster.global.mbarrier::complete_tx::bytes [%0], [%1, {%3, %4}], [%2];" ::"r"(dst), "l"(m), "r"(bar), "r"(c0), "r"(c1) : "memory");
}
__device__ __forceinline__ void tma_2d_mc(uint32_t dst, const CUtensorMap* m, uint32_t bar, int c0, int c1) {
  asm volatile("cp.async.bulk.tensor.2d.shared::cluster.global.mbarrier::complete_tx::bytes.multicast::cluster [%0], [%1, {%3, %4}], [%2], %5;" ::"r"(dst), "l"(m), "r"(bar), "r"(c0), "r"(c1), "h"((uint16_t)3) : "memory");
}
__device__ __forceinline__ void tma_3d_mc(uint32_t dst, const CUtensorMap* m, uint32_t bar, int c0, int c1, int c2) {
  asm volatile("cp.async.bulk.tensor.3d.shared::cluster.global.mbarrier::complete_tx::bytes.multicast::cluster [%0], [%1, {%3, %4, %5}], [%2], %6;" ::"r"(dst), "l"(m), "r"(bar), "r"(c0), "r"(c1), "r"(c2), "h"((uint16_t)3) : "memory");
}
__device__ __forceinline__ void tma_store_2d(const CUtensorMap* m, uint32_t src, int c0, int c1) {
  asm volatile("cp.async.bulk.tensor.2d.global.shared::cta.bulk_group [%0, {%2, %3}], [%1];" ::"l"(m), "r"(src), "r"(c0), "r"(c1) : "memory");
}
__device__ __forceinline__ void bulk_g2s(uint32_t dst, const void* src, uint32_t bytes, uint32_t bar) {
  asm volatile("cp.async.bulk.shared::cluster.global.mbarrier::complete_tx::bytes [%0], [%1], %2, [%3];" ::"r"(dst), "l"(src), "r"(bytes), "r"(bar) : "memory");
}
__device__ __forceinline__ void bulk_reduce_f32(void* dst, uint32_t src, uint32_t bytes) {
  asm volatile("cp.reduce.async.bulk.global.shared::cta.bulk_group.add.f32 [%0], [%1], %2;" ::"l"(dst), "r"(src), "r"(bytes) : "memory");
}
__device__ __forceinline__ void bulk_prefetch_l2(const void* src, uint32_t bytes) { asm volatile("cp.async.bulk.prefetch.L2.global [%0], %1;" ::"l"(src), "r"(bytes) : "memory"); }
__device__ __forceinline__ void bulk_commit() { asm volatile("cp.async.bulk.commit_group;" ::: "memory"); }
__device__ __forceinline__ void bulk_wait_read0() { asm volatile("cp.async.bulk.wait_group.read 0;" ::: "memory"); }
__device__ __forceinline__ void bulk_wait0() { asm volatile("cp.async.bulk.wait_group 0;" ::: "memory"); }
__device__ __forceinline__ void prefetch_map(const CUtensorMap* m) { asm volatile("prefetch.tensormap [%0];" ::"l"(m) : "memory"); }
__device__ __forceinline__ void cluster_arrive_relaxed() { asm volatile("barrier.cluster.arrive.relaxed.aligned;" ::: "memory"); }
__device__ __forceinline__ void cluster_wait() { asm volatile("barrier.cluster.wait.acquire.aligned;" ::: "memory"); }
__device__ __forceinline__ void bar_sync(int id, int n) { asm volatile("bar.sync %0, %1;" ::"r"(id), "r"(n) : "memory"); }
__device__ __forceinline__ void bar_arrive(int id, int n) { asm volatile("bar.arrive %0, %1;" ::"r"(id), "r"(n) : "memory"); }
__device__ __forceinline__ void wgmma_fence() { asm volatile("wgmma.fence.sync.aligned;" ::: "memory"); }
__device__ __forceinline__ void wgmma_commit() { asm volatile("wgmma.commit_group.sync.aligned;" ::: "memory"); }
template <int N> __device__ __forceinline__ void wgmma_wait() { asm volatile("wgmma.wait_group.sync.aligned %0;" ::"n"(N) : "memory"); }
template <int N> __device__ __forceinline__ void fence_regs(float (&d)[N]) {
#pragma unroll
  for (int i = 0; i < N; i++) asm volatile("" : "+f"(d[i])::"memory");
}
__device__ __forceinline__ uint64_t mk_desc(uint32_t addr, uint32_t lbo, uint32_t sbo, uint32_t swz) {
  uint32_t lo = ((addr & 0x3FFFF) >> 4) | ((lbo >> 4) << 16);
  uint32_t hi = (sbo >> 4) | (swz << 30);
  return ((uint64_t)hi << 32) | lo;
}
__device__ __forceinline__ uint32_t pack_bf16(float lo, float hi) { uint32_t r; asm("cvt.rn.bf16x2.f32 %0, %1, %2;" : "=r"(r) : "f"(hi), "f"(lo)); return r; }
__device__ __forceinline__ float ex2(float x) { float r; asm("ex2.approx.ftz.f32 %0, %1;" : "=f"(r) : "f"(x)); return r; }
__device__ __forceinline__ float rcp(float x) { float r; asm("rcp.approx.ftz.f32 %0, %1;" : "=f"(r) : "f"(x)); return r; }
__device__ __forceinline__ float bf_lo(uint32_t v) { return __uint_as_float(v << 16); }
__device__ __forceinline__ float bf_hi(uint32_t v) { return __uint_as_float(v & 0xffff0000u); }
__device__ __forceinline__ float tanh_f(float x) { float r; asm("tanh.approx.f32 %0, %1;" : "=f"(r) : "f"(x)); return r; }
__device__ __forceinline__ float silu_half(float hv) { return fmaf(hv, tanh_f(hv), hv); }
__device__ __forceinline__ void mma16816(float (&c)[4], uint32_t a0, uint32_t a1, uint32_t a2, uint32_t a3, uint32_t b0, uint32_t b1) {
  asm volatile("mma.sync.aligned.m16n8k16.row.col.f32.bf16.bf16.f32 {%0,%1,%2,%3}, {%4,%5,%6,%7}, {%8,%9}, {%0,%1,%2,%3};"
               : "+f"(c[0]), "+f"(c[1]), "+f"(c[2]), "+f"(c[3]) : "r"(a0), "r"(a1), "r"(a2), "r"(a3), "r"(b0), "r"(b1));
}
__device__ __forceinline__ void sts128(uint32_t addr, uint32_t a, uint32_t b, uint32_t c, uint32_t d) { asm volatile("st.shared.v4.b32 [%0], {%1,%2,%3,%4};" ::"r"(addr), "r"(a), "r"(b), "r"(c), "r"(d) : "memory"); }
__device__ __forceinline__ void sts64(uint32_t addr, uint32_t a, uint32_t b) { asm volatile("st.shared.v2.b32 [%0], {%1,%2};" ::"r"(addr), "r"(a), "r"(b) : "memory"); }
__device__ __forceinline__ void sts32(uint32_t addr, uint32_t a) { asm volatile("st.shared.b32 [%0], %1;" ::"r"(addr), "r"(a) : "memory"); }
__device__ __forceinline__ uint32_t lds32(uint32_t addr) { uint32_t v; asm volatile("ld.shared.b32 %0, [%1];" : "=r"(v) : "r"(addr) : "memory"); return v; }
__device__ __forceinline__ float4 lds128f(uint32_t addr) { float4 v; asm volatile("ld.shared.v4.f32 {%0,%1,%2,%3}, [%4];" : "=f"(v.x), "=f"(v.y), "=f"(v.z), "=f"(v.w) : "r"(addr) : "memory"); return v; }
__device__ __forceinline__ void stmatrix_x4(uint32_t addr, uint32_t a, uint32_t b, uint32_t c, uint32_t d) {
  asm volatile("stmatrix.sync.aligned.m8n8.x4.shared.b16 [%0], {%1,%2,%3,%4};" ::"r"(addr), "r"(a), "r"(b), "r"(c), "r"(d) : "memory");
}
__device__ __forceinline__ void ldmatrix_x4(uint32_t (&r)[4], uint32_t addr) {
  asm volatile("ldmatrix.sync.aligned.m8n8.x4.shared.b16 {%0,%1,%2,%3}, [%4];" : "=r"(r[0]), "=r"(r[1]), "=r"(r[2]), "=r"(r[3]) : "r"(addr) : "memory");
}

template<int TB> __device__ __forceinline__ void wgmma_rs_n64(float (&d)[32], uint32_t a0, uint32_t a1, uint32_t a2, uint32_t a3, uint64_t db, int sd) {
  asm volatile("{\n.reg .pred p;\nsetp.ne.b32 p, %37, 0;\n"
    "wgmma.mma_async.sync.aligned.m64n64k16.f32.bf16.bf16 {%0, %1, %2, %3, %4, %5, %6, %7, %8, %9, %10, %11, %12, %13, %14, %15, %16, %17, %18, %19, %20, %21, %22, %23, %24, %25, %26, %27, %28, %29, %30, %31}, {%32, %33, %34, %35}, %36, p, 1, 1, %38;\n}\n"
    : "+f"(d[0]), "+f"(d[1]), "+f"(d[2]), "+f"(d[3]), "+f"(d[4]), "+f"(d[5]), "+f"(d[6]), "+f"(d[7]), "+f"(d[8]), "+f"(d[9]), "+f"(d[10]), "+f"(d[11]), "+f"(d[12]), "+f"(d[13]), "+f"(d[14]), "+f"(d[15]), "+f"(d[16]), "+f"(d[17]), "+f"(d[18]), "+f"(d[19]), "+f"(d[20]), "+f"(d[21]), "+f"(d[22]), "+f"(d[23]), "+f"(d[24]), "+f"(d[25]), "+f"(d[26]), "+f"(d[27]), "+f"(d[28]), "+f"(d[29]), "+f"(d[30]), "+f"(d[31])
    : "r"(a0), "r"(a1), "r"(a2), "r"(a3), "l"(db), "r"(sd), "n"(TB));
}
template<int TB> __device__ __forceinline__ void wgmma_rs_n80(float (&d)[40], uint32_t a0, uint32_t a1, uint32_t a2, uint32_t a3, uint64_t db, int sd) {
  asm volatile("{\n.reg .pred p;\nsetp.ne.b32 p, %45, 0;\n"
    "wgmma.mma_async.sync.aligned.m64n80k16.f32.bf16.bf16 {%0, %1, %2, %3, %4, %5, %6, %7, %8, %9, %10, %11, %12, %13, %14, %15, %16, %17, %18, %19, %20, %21, %22, %23, %24, %25, %26, %27, %28, %29, %30, %31, %32, %33, %34, %35, %36, %37, %38, %39}, {%40, %41, %42, %43}, %44, p, 1, 1, %46;\n}\n"
    : "+f"(d[0]), "+f"(d[1]), "+f"(d[2]), "+f"(d[3]), "+f"(d[4]), "+f"(d[5]), "+f"(d[6]), "+f"(d[7]), "+f"(d[8]), "+f"(d[9]), "+f"(d[10]), "+f"(d[11]), "+f"(d[12]), "+f"(d[13]), "+f"(d[14]), "+f"(d[15]), "+f"(d[16]), "+f"(d[17]), "+f"(d[18]), "+f"(d[19]), "+f"(d[20]), "+f"(d[21]), "+f"(d[22]), "+f"(d[23]), "+f"(d[24]), "+f"(d[25]), "+f"(d[26]), "+f"(d[27]), "+f"(d[28]), "+f"(d[29]), "+f"(d[30]), "+f"(d[31]), "+f"(d[32]), "+f"(d[33]), "+f"(d[34]), "+f"(d[35]), "+f"(d[36]), "+f"(d[37]), "+f"(d[38]), "+f"(d[39])
    : "r"(a0), "r"(a1), "r"(a2), "r"(a3), "l"(db), "r"(sd), "n"(TB));
}
template<int TA, int TB> __device__ __forceinline__ void wgmma_ss_n24(float (&d)[12], uint64_t da, uint64_t db, int sd) {
  asm volatile("{\n.reg .pred p;\nsetp.ne.b32 p, %14, 0;\n"
    "wgmma.mma_async.sync.aligned.m64n24k16.f32.bf16.bf16 {%0, %1, %2, %3, %4, %5, %6, %7, %8, %9, %10, %11}, %12, %13, p, 1, 1, %15, %16;\n}\n"
    : "+f"(d[0]), "+f"(d[1]), "+f"(d[2]), "+f"(d[3]), "+f"(d[4]), "+f"(d[5]), "+f"(d[6]), "+f"(d[7]), "+f"(d[8]), "+f"(d[9]), "+f"(d[10]), "+f"(d[11])
    : "l"(da), "l"(db), "r"(sd), "n"(TA), "n"(TB));
}
template<int TA, int TB> __device__ __forceinline__ void wgmma_ss_n96(float (&d)[48], uint64_t da, uint64_t db, int sd) {
  asm volatile("{\n.reg .pred p;\nsetp.ne.b32 p, %50, 0;\n"
    "wgmma.mma_async.sync.aligned.m64n96k16.f32.bf16.bf16 {%0, %1, %2, %3, %4, %5, %6, %7, %8, %9, %10, %11, %12, %13, %14, %15, %16, %17, %18, %19, %20, %21, %22, %23, %24, %25, %26, %27, %28, %29, %30, %31, %32, %33, %34, %35, %36, %37, %38, %39, %40, %41, %42, %43, %44, %45, %46, %47}, %48, %49, p, 1, 1, %51, %52;\n}\n"
    : "+f"(d[0]), "+f"(d[1]), "+f"(d[2]), "+f"(d[3]), "+f"(d[4]), "+f"(d[5]), "+f"(d[6]), "+f"(d[7]), "+f"(d[8]), "+f"(d[9]), "+f"(d[10]), "+f"(d[11]), "+f"(d[12]), "+f"(d[13]), "+f"(d[14]), "+f"(d[15]), "+f"(d[16]), "+f"(d[17]), "+f"(d[18]), "+f"(d[19]), "+f"(d[20]), "+f"(d[21]), "+f"(d[22]), "+f"(d[23]), "+f"(d[24]), "+f"(d[25]), "+f"(d[26]), "+f"(d[27]), "+f"(d[28]), "+f"(d[29]), "+f"(d[30]), "+f"(d[31]), "+f"(d[32]), "+f"(d[33]), "+f"(d[34]), "+f"(d[35]), "+f"(d[36]), "+f"(d[37]), "+f"(d[38]), "+f"(d[39]), "+f"(d[40]), "+f"(d[41]), "+f"(d[42]), "+f"(d[43]), "+f"(d[44]), "+f"(d[45]), "+f"(d[46]), "+f"(d[47])
    : "l"(da), "l"(db), "r"(sd), "n"(TA), "n"(TB));
}
template<int TA, int TB> __device__ __forceinline__ void wgmma_ss_n160(float (&d)[80], uint64_t da, uint64_t db, int sd) {
  asm volatile("{\n.reg .pred p;\nsetp.ne.b32 p, %82, 0;\n"
    "wgmma.mma_async.sync.aligned.m64n160k16.f32.bf16.bf16 {%0, %1, %2, %3, %4, %5, %6, %7, %8, %9, %10, %11, %12, %13, %14, %15, %16, %17, %18, %19, %20, %21, %22, %23, %24, %25, %26, %27, %28, %29, %30, %31, %32, %33, %34, %35, %36, %37, %38, %39, %40, %41, %42, %43, %44, %45, %46, %47, %48, %49, %50, %51, %52, %53, %54, %55, %56, %57, %58, %59, %60, %61, %62, %63, %64, %65, %66, %67, %68, %69, %70, %71, %72, %73, %74, %75, %76, %77, %78, %79}, %80, %81, p, 1, 1, %83, %84;\n}\n"
    : "+f"(d[0]), "+f"(d[1]), "+f"(d[2]), "+f"(d[3]), "+f"(d[4]), "+f"(d[5]), "+f"(d[6]), "+f"(d[7]), "+f"(d[8]), "+f"(d[9]), "+f"(d[10]), "+f"(d[11]), "+f"(d[12]), "+f"(d[13]), "+f"(d[14]), "+f"(d[15]), "+f"(d[16]), "+f"(d[17]), "+f"(d[18]), "+f"(d[19]), "+f"(d[20]), "+f"(d[21]), "+f"(d[22]), "+f"(d[23]), "+f"(d[24]), "+f"(d[25]), "+f"(d[26]), "+f"(d[27]), "+f"(d[28]), "+f"(d[29]), "+f"(d[30]), "+f"(d[31]), "+f"(d[32]), "+f"(d[33]), "+f"(d[34]), "+f"(d[35]), "+f"(d[36]), "+f"(d[37]), "+f"(d[38]), "+f"(d[39]), "+f"(d[40]), "+f"(d[41]), "+f"(d[42]), "+f"(d[43]), "+f"(d[44]), "+f"(d[45]), "+f"(d[46]), "+f"(d[47]), "+f"(d[48]), "+f"(d[49]), "+f"(d[50]), "+f"(d[51]), "+f"(d[52]), "+f"(d[53]), "+f"(d[54]), "+f"(d[55]), "+f"(d[56]), "+f"(d[57]), "+f"(d[58]), "+f"(d[59]), "+f"(d[60]), "+f"(d[61]), "+f"(d[62]), "+f"(d[63]), "+f"(d[64]), "+f"(d[65]), "+f"(d[66]), "+f"(d[67]), "+f"(d[68]), "+f"(d[69]), "+f"(d[70]), "+f"(d[71]), "+f"(d[72]), "+f"(d[73]), "+f"(d[74]), "+f"(d[75]), "+f"(d[76]), "+f"(d[77]), "+f"(d[78]), "+f"(d[79])
    : "l"(da), "l"(db), "r"(sd), "n"(TA), "n"(TB));
}

#define TSTAMP(i)
#define TSTAMPL(i)
#define GSTAMP(i)
#define TDUMP()

__device__ __forceinline__ uint32_t ring_slot(uint32_t n) { return (0x32765410u >> (4 * (n & 7))) & 7u; }
__device__ __forceinline__ uint32_t ring_par(uint32_t n) { return ((0x38u >> (n & 7)) ^ (n >> 3)) & 1u; }

__device__ __forceinline__ void release_slot(uint32_t relb, uint32_t slot) {
  if (relb) asm volatile("mbarrier.arrive.shared::cluster.b64 _, [%0];" ::"r"(relb + 8 * (B_EMPTY + slot)) : "memory");
}

template <int N, bool KMAJOR>
__device__ __forceinline__ void p1_mainloop(float (&acc)[N / 2], const uint32_t (&A)[40][4], uint32_t sbase, uint32_t& n, bool first, int w, uint32_t relb) {
  const uint32_t bars = sbase + OFF_BAR;
  bar_sync(1 + w, 256);
  uint32_t prev = 0;
#pragma unroll
  for (int sl = 0; sl < 5; sl++) {
    const uint32_t slot = first ? (sl < 3 ? 5 + sl : sl - 1) : ring_slot(n);
    const uint32_t par = first ? (sl < 3 ? 0u : 1u) : ring_par(n);
    mbar_wait(bars, B_FULL + slot, par);
    const uint64_t d0 = mk_desc(sbase + OFF_RING + slot * SLOT_BYTES, 16, 1024, 1);
    wgmma_fence();
#pragma unroll
    for (int q = 0; q < 8; q++) {
      const int c = 8 * sl + q;
      const uint32_t off = KMAJOR ? ((q >> 2) * 10240 + (q & 3) * 32) : q * 2048;
      if constexpr (N == 64) wgmma_rs_n64<1>(acc, A[c][0], A[c][1], A[c][2], A[c][3], d0 + (off >> 4), (sl | q) != 0);
      else wgmma_rs_n80<0>(acc, A[c][0], A[c][1], A[c][2], A[c][3], d0 + (off >> 4), (sl | q) != 0);
    }
    wgmma_commit();
    if (sl == 4) bar_arrive(1 + (w ^ 1), 256);
    if (sl > 0) { wgmma_wait<1>(); release_slot(relb, prev); }
    prev = slot;
    if (!first) n++;
  }
  wgmma_wait<0>();
  release_slot(relb, prev);
  fence_regs(acc);
}

template <int HALF>
__device__ __forceinline__ void feat_row(float (&acc)[40], float c, uint32_t addr) {
#define AV(i) acc[4 * ((i) >> 1) + HALF + ((i) & 1)]
  float mxa[5], mna[5];
#pragma unroll
  for (int i = 0; i < 5; i++) {
    mxa[i] = fmaxf(fmaxf(AV(4 * i), AV(4 * i + 1)), fmaxf(AV(4 * i + 2), AV(4 * i + 3)));
    mna[i] = fminf(fminf(AV(4 * i), AV(4 * i + 1)), fminf(AV(4 * i + 2), AV(4 * i + 3)));
  }
  const float mx = fmaxf(fmaxf(fmaxf(mxa[0], mxa[1]), fmaxf(mxa[2], mxa[3])), mxa[4]);
  const float mn = fminf(fminf(fminf(mna[0], mna[1]), fminf(mna[2], mna[3])), mna[4]);
  const float bp = -mx * c, bn = mn * c;
  float en[20];
  float spa[2] = {0.f, 0.f}, sna[2] = {0.f, 0.f};
#pragma unroll
  for (int i = 0; i < 20; i++) {
    const float v = AV(i);
    en[i] = ex2(fmaf(v, -c, bn));
    AV(i) = ex2(fmaf(v, c, bp));
    if (i < 2) { sna[i] = en[i]; spa[i] = AV(i); }
    else { sna[i & 1] += en[i]; spa[i & 1] += AV(i); }
  }
#undef AV
  const float sp = spa[0] + spa[1], sn = sna[0] + sna[1];
  const float rp = rcp(sp), rn = rcp(sn);
#define PV(i) (acc[4 * ((i) >> 1) + HALF + ((i) & 1)] * rp)
#define NV(i) (en[i] * rn)
  sts128(addr + 0 * CH, pack_bf16(PV(0), PV(1)), pack_bf16(PV(2), PV(3)), pack_bf16(PV(4), PV(5)), pack_bf16(PV(6), PV(7)));
  sts128(addr + 1 * CH, pack_bf16(PV(8), PV(9)), pack_bf16(PV(10), PV(11)), pack_bf16(PV(12), PV(13)), pack_bf16(PV(14), PV(15)));
  sts128(addr + 2 * CH, pack_bf16(PV(16), PV(17)), pack_bf16(PV(18), PV(19)), pack_bf16(NV(0), NV(1)), pack_bf16(NV(2), NV(3)));
  sts128(addr + 3 * CH, pack_bf16(NV(4), NV(5)), pack_bf16(NV(6), NV(7)), pack_bf16(NV(8), NV(9)), pack_bf16(NV(10), NV(11)));
  sts128(addr + 4 * CH, pack_bf16(NV(12), NV(13)), pack_bf16(NV(14), NV(15)), pack_bf16(NV(16), NV(17)), pack_bf16(NV(18), NV(19)));
#undef PV
#undef NV
}

template <int HALF>
__device__ __forceinline__ void v_row(const float (&acc)[40], float rs, uint32_t addr) {
#define VV(i) (acc[4 * ((i) >> 1) + HALF + ((i) & 1)] * rs)
  sts128(addr + 0 * CH, pack_bf16(VV(0), VV(1)), pack_bf16(VV(2), VV(3)), pack_bf16(VV(4), VV(5)), pack_bf16(VV(6), VV(7)));
  sts128(addr + 1 * CH, pack_bf16(VV(8), VV(9)), pack_bf16(VV(10), VV(11)), pack_bf16(VV(12), VV(13)), pack_bf16(VV(14), VV(15)));
  sts128(addr + 2 * CH, pack_bf16(VV(16), VV(17)), pack_bf16(VV(18), VV(19)), 0x00003F80u, 0u);
#undef VV
}

template <int N>
__device__ __forceinline__ void p2_issue(float (&acc)[N / 2], bool first, uint32_t sbase, uint32_t n, int w) {
  const uint32_t bars = sbase + OFF_BAR;
  const uint32_t sa = ring_slot(n), sb = ring_slot(n + 1);
  mbar_wait(bars, B_FULL + sa, ring_par(n));
  mbar_wait(bars, B_FULL + sb, ring_par(n + 1));
  const uint64_t da = mk_desc(sbase + OFF_RING + sa * SLOT_BYTES + w * 8192, 16, 1024, 1);
  const uint64_t db = mk_desc(sbase + OFF_RING + sb * SLOT_BYTES, 2048, 512, 2);
  constexpr uint32_t HALF = N == 160 ? 10240 : 6144;
  wgmma_fence();
#pragma unroll
  for (int q = 0; q < 4; q++) {
    if constexpr (N == 160) wgmma_ss_n160<0, 1>(acc, da + ((q * 32) >> 4), db + (((q >> 1) * HALF + (q & 1) * 1024) >> 4), !first || q != 0);
    else wgmma_ss_n96<0, 1>(acc, da + ((q * 32) >> 4), db + (((q >> 1) * HALF + (q & 1) * 1024) >> 4), !first || q != 0);
  }
  wgmma_commit();
}
__device__ __forceinline__ void p2_retire(uint32_t relb, uint32_t n) {
  release_slot(relb, ring_slot(n - 2));
  release_slot(relb, ring_slot(n - 1));
}

__global__ void __cluster_dims__(2, 1, 1) __launch_bounds__(NTHREADS, 1)
fused_kernel(const __grid_constant__ Maps maps, const __nv_bfloat16* __restrict__ x, const __nv_bfloat16* __restrict__ wphi,
             const __nv_bfloat16* __restrict__ wqkv, const __nv_bfloat16* __restrict__ w1, const __nv_bfloat16* __restrict__ w2,
             const __nv_bfloat16* __restrict__ wo, Scratch* __restrict__ scr) {
  extern __shared__ uint8_t smem_raw[];
  const uint32_t sbase = (smem_u32(smem_raw) + 1023) & ~1023u;
  const uint32_t bars = sbase + OFF_BAR;
  const int warp = __shfl_sync(0xffffffffu, (int)(threadIdx.x >> 5), 0), lane = threadIdx.x & 31;
  const int b = blockIdx.x;
  const uint32_t rank = b & 1;
  const int cl = b >> 1;
  int g_set, g_mem;
  if (cl < 4) { g_set = 15; g_mem = cl; }
  else if (cl < 36) { g_set = (cl - 4) & 7; g_mem = (cl - 4) >> 3; }
  else { g_set = 8 + (cl - 36) % 7; g_mem = (cl - 36) / 7; }
  const int rbp = g_set & 7, j = 4 * (g_set >> 3) + g_mem;
  const int rb = 2 * rbp + (int)rank;
  if (threadIdx.x == 0) GSTAMP(50);
  if (threadIdx.x < 150) asm volatile("prefetch.global.L2 [%0];" ::"l"(reinterpret_cast<const uint8_t*>(wqkv) + (b * 150 + threadIdx.x) * 128));
  const int f_part = b / 40, f_grp = (b % 40) / 10, f_q = b % 10;
  const int nt = g_mem, kh = g_set >> 3, rb2 = rb;

  if (warp >= 8) {
    asm volatile("setmaxnreg.dec.sync.aligned.u32 24;");
    auto load_x = [&](uint32_t slot, uint32_t par, int half, int c) {
      const uint32_t fb = bars + 8 * (B_FULL + slot), dst = sbase + OFF_RING + slot * SLOT_BYTES;
      mbar_wait(bars, B_EMPTY + slot, par ^ 1);
      mbar_expect_tx(fb, 16384);
      tma_2d(dst, &maps.x, fb, 128 * c, 128 * rb + 64 * half);
      tma_2d(dst + 8192, &maps.x, fb, 128 * c + 64, 128 * rb + 64 * half);
    };
    auto load_b = [&](uint32_t slot, uint32_t par, bool isH, int col, int sl) {
      const uint32_t fb = bars + 8 * (B_FULL + slot), dst = sbase + OFF_RING + slot * SLOT_BYTES;
      mbar_wait(bars, B_EMPTY + slot, par ^ 1);
      if (isH) { mbar_expect_tx(fb, 16384); tma_2d_mc(dst + rank * 8192, &maps.w1, fb, col, 128 * sl + 64 * (int)rank); }
      else { mbar_expect_tx(fb, 20480); tma_2d_mc(dst + rank * 10240, &maps.wp, fb, 128 * sl + 64 * (int)rank, col); }
    };
    if (warp == 8) {
      if (lane == 0) {
        prefetch_map(&maps.raw); prefetch_map(&maps.x);
        mbar_init(bars + 8 * B_FOLD, 1);
        for (int s = 0; s < NSLOT; s++) { mbar_init(bars + 8 * (B_FULL + s), 1); mbar_init(bars + 8 * (B_EMPTY + s), 4); }
        mbar_init(bars + 8 * (B_STGFULL + 0), 128); mbar_init(bars + 8 * (B_STGFULL + 1), 128);
        mbar_init(bars + 8 * (B_STGFREE + 0), 1); mbar_init(bars + 8 * (B_STGFREE + 1), 1);
        mbar_init(bars + 8 * B_VFREE, 1); mbar_init(bars + 8 * B_KVB, 1); mbar_init(bars + 8 * B_KVRAW, 1); mbar_init(bars + 8 * B_EPOCH, 1);
        mbar_init(bars + 8 * B_XRES, 1); mbar_init(bars + 8 * (B_XRES + 1), 1);
        mbar_init(bars + 8 * B_FOLDDONE, 2); mbar_init(bars + 8 * B_XD, 1); mbar_init(bars + 8 * (B_XD + 1), 1);
        asm volatile("fence.mbarrier_init.release.cluster;" ::: "memory");
      }
      __syncwarp();
    }
    cluster_arrive_relaxed();
    if (warp == 8 && lane == 0) {
      if (b < 120) {
        mbar_expect_tx(bars + 8 * B_FOLD, 20480 + (f_part < 2 ? 6400 : 0));
        tma_2d(sbase + OFF_W, &maps.raw, bars + 8 * B_FOLD, 640 * f_part + 160 * f_grp, 64 * f_q);
        if (f_part < 2) bulk_g2s(sbase + OFF_W + 20480, wphi + f_grp * 3200, 6400, bars + 8 * B_FOLD);
      }
      for (int c = 0; c < 5; c++) load_x(c, 0, 0, c);
      prefetch_map(&maps.w1);
      TSTAMPL(45);
    }
    __syncwarp();
    cluster_wait();
    if (warp == 8) {
      if (lane == 0) {
        load_b(5, 0, true, 192 * j, 0); load_b(6, 0, true, 192 * j, 1); load_b(7, 0, true, 192 * j, 2);
        mbar_wait(bars, B_FOLDDONE, 0);
        for (int c = 3; c < 5; c++) {
          const uint32_t fb = bars + 8 * (B_XD + c - 3), dst = sbase + OFF_W + 8192 + (c - 3) * 16384;
          mbar_expect_tx(fb, 16384);
          tma_2d(dst, &maps.x, fb, 128 * c, 128 * rb + 64);
          tma_2d(dst + 8192, &maps.x, fb, 128 * c + 64, 128 * rb + 64);
        }
        load_x(0, 1, 1, 0); load_x(1, 1, 1, 1);
        load_b(2, 1, true, 192 * j, 3); load_b(3, 1, true, 192 * j, 4);
        load_x(4, 1, 1, 2);
        prefetch_map(&maps.wp); prefetch_map(&maps.h_ld); prefetch_map(&maps.w2); prefetch_map(&maps.o_ld); prefetch_map(&maps.wo);
        uint32_t n = 0;
        mbar_wait(bars, B_EPOCH, 0);
        const unsigned epoch = lds32(bars + 256);
#pragma unroll 1
        for (int T = 1; T < 6; T++) {
          const bool isH = (T == 3 || T == 4);
          const int sp = (T == 1) ? 1 : (T == 2) ? 0 : 2;
          if (!isH) { wait_counter(bars, &scr->cnt.fold[(sp * 8 + j) * 8], (epoch + 1) * 10); fence_async_global(); }
          const int col = isH ? 192 * j + 64 * (T - 2) : 240 * j + 80 * sp;
#pragma unroll 1
          for (int sl = 0; sl < 5; sl++, n++) load_b(ring_slot(n), ring_par(n), isH, col, sl);
        }
        TSTAMPL(40);
#pragma unroll 1
        for (int ks = 0; ks < 22; ks++) {
          int kcol; const CUtensorMap* ma = &maps.h_ld;
          if (ks < 12) {
            const int th = ks >> 2;
            kcol = 64 * (3 * (4 * kh + (ks & 3)) + th);
            if ((ks & 3) == 0) { wait_counter(bars, &scr->rb[rb2].h[8 * th], (epoch + 1) * 16); fence_async_global(); }
          }
          else { kcol = 64 * (ks - 12); ma = &maps.o_ld; if (ks == 12) { wait_counter(bars, &scr->rb[rb2].o[0], (epoch + 1) * 16); fence_async_global(); } }
          if (ks == 0) TSTAMPL(58);
          if (ks == 4) TSTAMPL(59);
          if (ks == 8) TSTAMPL(60);
          if (ks == 12) TSTAMPL(61);
          {
            const uint32_t slot = ring_slot(n), fb = bars + 8 * (B_FULL + slot);
            mbar_wait(bars, B_EMPTY + slot, ring_par(n) ^ 1);
            mbar_expect_tx(fb, 16384);
            tma_2d(sbase + OFF_RING + slot * SLOT_BYTES, ma, fb, kcol, 128 * rb2);
            n++;
          }
          {
            const uint32_t slot = ring_slot(n), fb = bars + 8 * (B_FULL + slot), dst = sbase + OFF_RING + slot * SLOT_BYTES;
            mbar_wait(bars, B_EMPTY + slot, ring_par(n) ^ 1);
            if (ks < 12) { mbar_expect_tx(fb, 20480); tma_3d_mc(dst + rank * 10240, &maps.w2, fb, 0, kcol + 32 * (int)rank, 5 * nt); }
            else { mbar_expect_tx(fb, 12288); tma_3d_mc(dst + rank * 6144, &maps.wo, fb, 0, kcol + 32 * (int)rank, 5 * nt + 2 * kh); }
            n++;
          }
        }
        TSTAMPL(41);
      }
    } else if (warp == 9 || warp == 10) {
      if (lane == 0) {
        const int w = warp - 9;
        const uint32_t src = sbase + OFF_W + w * W_BYTES;
        const int row = 128 * rb + 64 * w;
        prefetch_map(&maps.h_st); prefetch_map(&maps.o_st); prefetch_map(&maps.out_st); prefetch_map(&maps.xres);
        mbar_wait(bars, B_EPOCH, 0);
        const unsigned epoch = lds32(bars + 256);
#pragma unroll 1
        for (int n = 0; n < 6; n++) {
          mbar_wait_lazy(bars, B_STGFULL + w, n & 1);
          unsigned* flag;
          if (n == 1) { bulk_reduce_f32(scr->kv[epoch & 1] + j * KV_FLOATS, src, KV_FLOATS * 4); flag = &scr->cnt.kv[j * 8]; }
          else if (n < 4) { const int th = n == 0 ? 0 : n - 1; tma_store_2d(&maps.h_st, src, 192 * j + 64 * th, row); flag = &scr->rb[rb].h[th * 8]; }
          else if (n == 4) { tma_store_2d(&maps.o_st, src, 80 * j, row); flag = &scr->rb[rb].o[0]; }
          else { tma_store_2d(&maps.out_st, src, 160 * nt + 80 * kh, 128 * rb2 + 64 * w); flag = nullptr; }
          bulk_commit();
          bulk_wait_read0();
          mbar_arrive(bars + 8 * (B_STGFREE + w));
          if (n == 5) break;
          if (n == 4) {
            mbar_expect_tx(bars + 8 * (B_XRES + w), 10240);
            tma_2d(src + 10240, &maps.xres, bars + 8 * (B_XRES + w), 160 * nt + 80 * kh, 128 * rb2 + 64 * w);
          }
          bulk_wait0();
          if (n == 1 && w == 1) TSTAMPL(54);
          if (n == 4 && w == 1) TSTAMPL(57);
          if (flag) red_release(flag, 1);
        }
        if (b == 0 && w == 0) scr->cnt.epoch = epoch + 1;
      }
    } else {
      unsigned epoch = 0;
      if (lane == 0) {
        epoch = ld_acquire(&scr->cnt.epoch);
        sts32(bars + 256, epoch);
        mbar_arrive(bars + 8 * B_EPOCH);
        bulk_prefetch_l2(reinterpret_cast<const uint8_t*>(x) + b * 20480, 20480);
      }
      epoch = __shfl_sync(~0u, epoch, 0);
      float4* kvn = reinterpret_cast<float4*>(scr->kv[(epoch + 1) & 1]) + b * 60;
      for (int i = lane; i < 60; i += 32) kvn[i] = make_float4(0.f, 0.f, 0.f, 0.f);
      bar_sync(5, 288);
      if (lane < 2 && b < 120) { fence_async_global(); red_release(&scr->cnt.fold[((2 - f_part) * 8 + 2 * f_grp + lane) * 8], 1); }
      if (lane == 0) {
        bulk_prefetch_l2(reinterpret_cast<const uint8_t*>(w1) + b * 15360, 15360);
        bulk_prefetch_l2(reinterpret_cast<const uint8_t*>(w2) + b * 15360, 15360);
        bulk_prefetch_l2(reinterpret_cast<const uint8_t*>(wo) + b * 6400, 6400);
      }
      mbar_wait_lazy(bars, B_VFREE, 0);
      mbar_wait_lazy(bars, B_VFREE, 1);
      __syncwarp();
      if (lane == 0) {
        TSTAMPL(55);
        wait_counter(bars, &scr->cnt.kv[j * 8], (epoch + 1) * 32);
        TSTAMPL(56);
        fence_async_global();
        mbar_expect_tx(bars + 8 * B_KVRAW, KV_FLOATS * 4);
        bulk_g2s(sbase + OFF_KVB, scr->kv[epoch & 1] + j * KV_FLOATS, KV_FLOATS * 4, bars + 8 * B_KVRAW);
      }
    }
    __syncwarp();
    cluster_arrive_relaxed();
    cluster_wait();
  } else {
    asm volatile("setmaxnreg.inc.sync.aligned.u32 240;");
    const int w = warp >> 2, wi = warp & 3, tid128 = threadIdx.x & 127;
    const int g = lane >> 2, t = lane & 3;
    uint32_t relb = 0;
    if (tid128 == 0 || tid128 == 32) asm volatile("mapa.shared::cluster.u32 %0, %1, %2;" : "=r"(relb) : "r"(bars), "r"(tid128 == 0 ? rank : rank ^ 1));
    uint32_t A[40][4];
    float s0[4] = {0.f, 0.f, 0.f, 0.f}, ga[4] = {0.f, 0.f, 0.f, 0.f}, gb[4] = {0.f, 0.f, 0.f, 0.f};
    auto take_x = [&](int c, uint32_t slot, uint32_t par) {
      const bool ring = slot < 8;
      mbar_wait(bars, ring ? B_FULL + slot : B_XD + slot - 8, par);
      const int m = lane >> 3, rr = lane & 7;
      const uint32_t ra = (ring ? sbase + OFF_RING + slot * SLOT_BYTES : sbase + OFF_W + 8192 + (slot - 8) * 16384) + (16 * wi + (m & 1) * 8 + rr) * 128;
#pragma unroll
      for (int q = 0; q < 8; q++) {
        ldmatrix_x4(A[8 * c + q], ra + (q >> 2) * 8192 + (((2 * (q & 3) + (m >> 1)) ^ rr) << 4));
        mma16816(s0, A[8 * c + q][0], A[8 * c + q][1], A[8 * c + q][2], A[8 * c + q][3], 0x3F803F80u, 0x3F803F80u);
        mma16816(ga, A[8 * c + q][0], A[8 * c + q][1], A[8 * c + q][2], A[8 * c + q][3], A[8 * c + q][0], A[8 * c + q][2]);
        mma16816(gb, A[8 * c + q][0], A[8 * c + q][1], A[8 * c + q][2], A[8 * c + q][3], A[8 * c + q][1], A[8 * c + q][3]);
      }
      if (ring) {
        bar_sync(3 + w, 128);
        release_slot(relb, slot); release_slot(relb, slot);
      }
    };
    cluster_arrive_relaxed();
    {
      cluster_wait();
      if (b < 120) {
        const int hl = 4 * w + wi, head = 8 * f_grp + hl, jj = head >> 2, th = head & 3, sp = 2 - f_part;
        mbar_wait(bars, B_FOLD, 0);
        TSTAMP(w == 1 ? 44 : 42);
        const uint32_t ph = sbase + OFF_W + 20480 + hl * 800;
        auto PH = [&](int d, int f) -> uint32_t {
          if (d >= 20 || f >= 20) return 0u;
          if (f_part == 2) return d == f ? 0x3F80u : 0u;
          uint16_t v; asm volatile("ld.shared.u16 %0, [%1];" : "=h"(v) : "r"(ph + (d * 20 + f) * 2) : "memory");
          return v;
        };
        auto PH2 = [&](int d, int f) -> uint32_t { return PH(d, f) | (PH(d + 1, f) << 16); };
        const uint32_t a00 = PH2(2 * t, g), a01 = PH2(2 * t, g + 8), a02 = PH2(2 * t + 8, g), a03 = PH2(2 * t + 8, g + 8);
        const uint32_t a10 = PH2(16 + 2 * t, g), a11 = PH2(16 + 2 * t, g + 8);
        const uint32_t a20 = PH2(2 * t, 16 + g), a22 = PH2(2 * t + 8, 16 + g);
        const uint32_t a30 = PH2(16 + 2 * t, 16 + g);
        const int rbase = 240 * jj + 80 * sp + 2 * th;
        __nv_bfloat16* d0 = scr->wp + (size_t)(rbase + 8 * (g >> 1) + (g & 1)) * DM + 64 * f_q + 8 * t;
#pragma unroll
        for (int blk = 0; blk < 2; blk++) {
          uint32_t r0[4], r1[4], r2[4];
#pragma unroll
          for (int nb = 0; nb < 4; nb++) {
            const uint32_t ba = sbase + OFF_W + (32 * blk + 8 * (g >> 1) + 2 * nb + (g & 1)) * 320 + hl * 40 + 4 * t;
            const uint32_t b0 = lds32(ba), b1 = lds32(ba + 16), b2 = (t < 2) ? lds32(ba + 32) : 0u;
            float c0[4] = {0.f, 0.f, 0.f, 0.f}, c1[4] = {0.f, 0.f, 0.f, 0.f};
            mma16816(c0, a00, a01, a02, a03, b0, b1);
            mma16816(c0, a10, a11, 0u, 0u, b2, 0u);
            mma16816(c1, a20, 0u, a22, 0u, b0, b1);
            mma16816(c1, a30, 0u, 0u, 0u, b2, 0u);
            r0[nb] = pack_bf16(c0[0], c0[1]); r1[nb] = pack_bf16(c0[2], c0[3]); r2[nb] = pack_bf16(c1[0], c1[1]);
          }
          *reinterpret_cast<uint4*>(d0 + 32 * blk) = make_uint4(r0[0], r0[1], r0[2], r0[3]);
          *reinterpret_cast<uint4*>(d0 + 32 * DM + 32 * blk) = make_uint4(r1[0], r1[1], r1[2], r1[3]);
          if (g < 4) *reinterpret_cast<uint4*>(d0 + 64 * DM + 32 * blk) = make_uint4(r2[0], r2[1], r2[2], r2[3]);
        }
      }
      bar_arrive(5, 288);
      bar_sync(3 + w, 128);
      if (tid128 == 0) mbar_arrive(bars + 8 * B_FOLDDONE);
      if (w == 1) bar_arrive(1, 256);
      TSTAMP(w == 1 ? 49 : 43);
    }
    if (w == 1) {
      take_x(3, 8, 0); take_x(4, 9, 0);
      bar_sync(6, 256);
      take_x(0, 0, 1); take_x(1, 1, 1);
      bar_sync(7, 256);
      TSTAMP(48);
      take_x(2, 4, 1);
    } else {
      take_x(0, 0, 0); take_x(1, 1, 0);
      bar_arrive(6, 256);
      take_x(2, 2, 0); take_x(3, 3, 0); take_x(4, 4, 0);
      bar_arrive(7, 256);
    }
    TSTAMP(w * 20 + 0);
    float rs0, rs1;
    {
      const float m0 = s0[0] * (1.0f / DM), m1 = s0[2] * (1.0f / DM);
      const int dl = (lane & 28) | (g >> 1);
      const float q0 = __shfl_sync(~0u, (g & 1) ? ga[1] : ga[0], dl), q1 = __shfl_sync(~0u, (g & 1) ? gb[3] : gb[2], dl);
      rs0 = rsqrtf(fmaxf(q0 * (1.0f / DM) - m0 * m0, 0.f) + 1e-5f);
      rs1 = rsqrtf(fmaxf(q1 * (1.0f / DM) - m1 * m1, 0.f) + 1e-5f);
      const __nv_bfloat162 mb0 = __float2bfloat162_rn(m0), mb1 = __float2bfloat162_rn(m1);
#pragma unroll
      for (int c = 0; c < 40; c++) {
#pragma unroll
        for (int i = 0; i < 4; i++) {
          __nv_bfloat162 v = *reinterpret_cast<__nv_bfloat162*>(&A[c][i]);
          v = __hsub2(v, (i & 1) ? mb1 : mb0);
          A[c][i] = *reinterpret_cast<uint32_t*>(&v);
        }
      }
    }
    TSTAMP(w * 20 + 1);
    uint32_t it = 0;
    const uint32_t rw = sbase + OFF_W + w * W_BYTES;
    const int srow = 16 * wi + g;
#pragma unroll 1
    for (int T = 0; T < 5; T++) {
      if (T == 0 || T >= 3) {
        float acc[32];
        p1_mainloop<64, false>(acc, A, sbase, it, T == 0, w, relb);
        TSTAMP(w * 20 + 2 + 2 * T);
        if (T == 3) mbar_wait(bars, B_STGFREE + w, 1);
        if (T == 4) mbar_wait(bars, B_STGFREE + w, 0);
        const int m = lane >> 3, rr = lane & 7;
        const float hs0 = 0.5f * rs0, hs1 = 0.5f * rs1;
        const uint32_t rowaddr = rw + (16 * wi + (m & 1) * 8 + rr) * 128;
#pragma unroll
        for (int q = 0; q < 4; q++) {
          const uint32_t r0 = pack_bf16(silu_half(acc[8 * q + 0] * hs0), silu_half(acc[8 * q + 1] * hs0));
          const uint32_t r1 = pack_bf16(silu_half(acc[8 * q + 2] * hs1), silu_half(acc[8 * q + 3] * hs1));
          const uint32_t r2 = pack_bf16(silu_half(acc[8 * q + 4] * hs0), silu_half(acc[8 * q + 5] * hs0));
          const uint32_t r3 = pack_bf16(silu_half(acc[8 * q + 6] * hs1), silu_half(acc[8 * q + 7] * hs1));
          stmatrix_x4(rowaddr + (((2 * q + (m >> 1)) ^ rr) << 4), r0, r1, r2, r3);
        }
        fence_async_smem();
        mbar_arrive(bars + 8 * (B_STGFULL + w));
      } else {
        float acc[40];
        p1_mainloop<80, true>(acc, A, sbase, it, false, w, relb);
        TSTAMP(w * 20 + 2 + 2 * T);
        const uint32_t vb = sbase + OFF_KVB;
        if (T == 2) {
          if (w == 1) mbar_wait(bars, B_VFREE, 0);
          v_row<0>(acc, rs0, vb + 3 * t * CH + srow * 16);
          v_row<2>(acc, rs1, vb + 3 * t * CH + (srow + 8) * 16);
          fence_async_smem();
          bar_sync(3 + w, 128);
          TSTAMP(w * 20 + 18);
          float D[4][12];
          wgmma_fence();
#pragma unroll
          for (int hh = 0; hh < 4; hh++) {
            const uint64_t da = mk_desc(rw + 5 * hh * CH, 128, CH, 0), db = mk_desc(vb + 3 * hh * CH, 128, CH, 0);
#pragma unroll
            for (int ks = 0; ks < 4; ks++) wgmma_ss_n24<1, 1>(D[hh], da + ks * 16, db + ks * 16, ks != 0);
          }
          wgmma_commit();
          wgmma_wait<0>();
          fence_regs(D[0]); fence_regs(D[1]); fence_regs(D[2]); fence_regs(D[3]);
          TSTAMP(w * 20 + 19);
          bar_sync(3 + w, 128);
          if (tid128 == 0) mbar_arrive(bars + 8 * B_VFREE);
          if (wi < 3) {
#pragma unroll
            for (int hh = 0; hh < 4; hh++) {
              const uint32_t da = rw + hh * 3840 + srow * 96 + 8 * t;
#pragma unroll
              for (int q = 0; q < 3; q++) {
                sts64(da + 32 * q, __float_as_uint(D[hh][4 * q]), __float_as_uint(D[hh][4 * q + 1]));
                if (wi < 2) sts64(da + 768 + 32 * q, __float_as_uint(D[hh][4 * q + 2]), __float_as_uint(D[hh][4 * q + 3]));
              }
            }
          }
          fence_async_smem();
          mbar_arrive(bars + 8 * (B_STGFULL + w));
        } else {
          mbar_wait(bars, B_STGFREE + w, 0);
          const uint32_t pa = rw + 5 * t * CH + srow * 16;
          feat_row<0>(acc, rs0 * 1.4426950408889634f, pa);
          feat_row<2>(acc, rs1 * 1.4426950408889634f, pa + 128);
          TSTAMP(w * 20 + 17);
        }
      }
      TSTAMP(w * 20 + 3 + 2 * T);
    }
    {
      const uint32_t vb = sbase + OFF_KVB;
      float acc[40];
      p1_mainloop<80, true>(acc, A, sbase, it, false, w, relb);
      TSTAMP(w * 20 + 12);
      mbar_wait(bars, B_STGFREE + w, 1);
      const uint32_t pa = rw + 5 * t * CH + srow * 16;
      feat_row<0>(acc, rs0 * 1.4426950408889634f, pa);
      feat_row<2>(acc, rs1 * 1.4426950408889634f, pa + 128);
      if (tid128 < 66) sts128(rw + 20 * CH + 16 * tid128, 0, 0, 0, 0);
      if (w == 0) {
        mbar_wait(bars, B_KVRAW, 0);
        TSTAMP(46);
        float4 v[2][6];
#pragma unroll
        for (int u = 0; u < 2; u++) {
          const int r = tid128 + 128 * u;
          if (r < 160) {
#pragma unroll
            for (int c = 0; c < 6; c++) v[u][c] = lds128f(vb + r * 96 + 16 * c);
          }
        }
        bar_sync(3, 128);
#pragma unroll
        for (int u = 0; u < 2; u++) {
          const int r = tid128 + 128 * u;
          if (r < 160) {
            const int head = (r * 1639) >> 16, f = r - 40 * head;
            const uint32_t dst = vb + head * KVB_HEAD + (f >> 3) * 128 + (f & 7) * 16;
#pragma unroll
            for (int c = 0; c < 3; c++)
              sts128(dst + 768 * c, pack_bf16(v[u][2 * c].x, v[u][2 * c].y), pack_bf16(v[u][2 * c].z, v[u][2 * c].w), pack_bf16(v[u][2 * c + 1].x, v[u][2 * c + 1].y), pack_bf16(v[u][2 * c + 1].z, v[u][2 * c + 1].w));
          }
        }
        if (tid128 < 96) sts128(vb + (tid128 / 24) * KVB_HEAD + ((tid128 % 24) >> 3) * 768 + 5 * 128 + (tid128 & 7) * 16, 0, 0, 0, 0);
      }
      fence_async_smem();
      bar_sync(3 + w, 128);
      if (w == 0) { if (tid128 == 0) mbar_arrive(bars + 8 * B_KVB); TSTAMP(47); }
      else mbar_wait(bars, B_KVB, 0);
      float D[4][12];
      wgmma_fence();
#pragma unroll
      for (int hh = 0; hh < 4; hh++) {
        const uint64_t da = mk_desc(rw + 5 * hh * CH, CH, 128, 0), db = mk_desc(vb + hh * KVB_HEAD, 128, 768, 0);
#pragma unroll
        for (int ks = 0; ks < 3; ks++) wgmma_ss_n24<0, 1>(D[hh], da + ks * ((2 * CH) >> 4), db + ks * 16, ks != 0);
      }
      wgmma_commit();
      wgmma_wait<0>();
      fence_regs(D[0]); fence_regs(D[1]); fence_regs(D[2]); fence_regs(D[3]);
      bar_sync(3 + w, 128);
#pragma unroll
      for (int hh = 0; hh < 4; hh++) {
        const float i0 = rcp(__shfl_sync(~0u, D[hh][8], (lane & 28) | 2) + 1e-6f);
        const float i1 = rcp(__shfl_sync(~0u, D[hh][10], (lane & 28) | 2) + 1e-6f);
        const uint32_t oa = rw + srow * 160 + (20 * hh + 2 * t) * 2;
#pragma unroll
        for (int q = 0; q < 3; q++) {
          if (q < 2 || t < 2) {
            sts32(oa + 16 * q, pack_bf16(D[hh][4 * q] * i0, D[hh][4 * q + 1] * i0));
            sts32(oa + 8 * 160 + 16 * q, pack_bf16(D[hh][4 * q + 2] * i1, D[hh][4 * q + 3] * i1));
          }
        }
      }
      fence_async_smem();
      mbar_arrive(bars + 8 * (B_STGFULL + w));
      TSTAMP(w * 20 + 13);
    }
    if (w == 0) bar_sync(1, 256);
    float G[80], Sa[48];
    uint4* pb = scr->rb[rb2].xch + nt * 2 * 1280 + w * 640 + tid128;
    uint4* outb = pb + (kh ^ 1) * 1280;
    uint4* inb = pb + kh * 1280;
    p2_issue<160>(G, true, sbase, it, w); it += 2;
#pragma unroll 1
    for (int ks = 1; ks < 12; ks++) {
      p2_issue<160>(G, false, sbase, it, w);
      wgmma_wait<1>();
      p2_retire(relb, it);
      it += 2;
    }
    p2_issue<96>(Sa, true, sbase, it, w);
    wgmma_wait<1>();
    p2_retire(relb, it);
    it += 2;
    fence_regs(G);
    {
      auto nz = [](uint32_t v) { return v == 0u ? 0x80000000u : v; };
      auto put = [&](uint4* p, const float* v) {
        asm volatile("st.relaxed.gpu.global.v4.b32 [%0], {%1,%2,%3,%4};" ::"l"(p), "r"(nz(pack_bf16(v[0], v[1]))), "r"(nz(pack_bf16(v[2], v[3]))),
                     "r"(nz(pack_bf16(v[4], v[5]))), "r"(nz(pack_bf16(v[6], v[7]))) : "memory");
      };
      if (kh == 0) {
#pragma unroll
        for (int i = 0; i < 5; i++) put(outb + i * 128, &G[40 + 8 * i]);
#pragma unroll
        for (int i = 0; i < 40; i++) G[40 + i] = G[i];
      } else {
#pragma unroll
        for (int i = 0; i < 5; i++) put(outb + i * 128, &G[8 * i]);
      }
      if (threadIdx.x == 0) TSTAMPL(62);
    }
#pragma unroll 1
    for (int ks = 1; ks < 10; ks++) {
      p2_issue<96>(Sa, false, sbase, it, w);
      wgmma_wait<1>();
      p2_retire(relb, it);
      it += 2;
    }
    float gv[40], sv[40];
    {
      auto get = [&](uint4* p) {
        uint4 v;
        asm volatile("ld.relaxed.gpu.global.v4.b32 {%0,%1,%2,%3}, [%4];" : "=r"(v.x), "=r"(v.y), "=r"(v.z), "=r"(v.w) : "l"(p) : "memory");
        return v;
      };
      auto ok = [](const uint4& v) { return v.x != 0u && v.y != 0u && v.z != 0u && v.w != 0u; };
      uint4 a[5];
#pragma unroll 1
      for (uint32_t tries = 0; tries < 0x100000u; tries++) {
        bool all = true;
#pragma unroll
        for (int i = 0; i < 5; i++) a[i] = get(inb + i * 128);
#pragma unroll
        for (int i = 0; i < 5; i++) all = all && ok(a[i]);
        if (__all_sync(~0u, all)) break;
        __nanosleep(200);
      }
      if (threadIdx.x == 0) TSTAMPL(63);
#pragma unroll
      for (int i = 0; i < 5; i++) {
        inb[i * 128] = make_uint4(0u, 0u, 0u, 0u);
        gv[8 * i] = G[40 + 8 * i] + bf_lo(a[i].x); gv[8 * i + 1] = G[41 + 8 * i] + bf_hi(a[i].x); gv[8 * i + 2] = G[42 + 8 * i] + bf_lo(a[i].y); gv[8 * i + 3] = G[43 + 8 * i] + bf_hi(a[i].y);
        gv[8 * i + 4] = G[44 + 8 * i] + bf_lo(a[i].z); gv[8 * i + 5] = G[45 + 8 * i] + bf_hi(a[i].z); gv[8 * i + 6] = G[46 + 8 * i] + bf_lo(a[i].w); gv[8 * i + 7] = G[47 + 8 * i] + bf_hi(a[i].w);
      }
    }
    wgmma_wait<0>();
    p2_retire(relb, it);
    fence_regs(Sa);
    TSTAMP(w * 20 + 14);
#pragma unroll
    for (int i = 0; i < 40; i++) sv[i] = kh ? Sa[8 + i] : Sa[i];
    TSTAMP(w * 20 + 15);
    mbar_wait(bars, B_STGFREE + w, 0);
    mbar_wait(bars, B_XRES + w, 0);
    {
      uint32_t xr[20];
#pragma unroll
      for (int q = 0; q < 10; q++) { xr[2 * q] = lds32(rw + 10240 + srow * 160 + 16 * q + 4 * t); xr[2 * q + 1] = lds32(rw + 10240 + (srow + 8) * 160 + 16 * q + 4 * t); }
      uint32_t o[20];
#pragma unroll
      for (int q = 0; q < 10; q++) {
        o[2 * q] = pack_bf16(fmaf(sv[4 * q], silu_half(0.5f * gv[4 * q]), bf_lo(xr[2 * q])), fmaf(sv[4 * q + 1], silu_half(0.5f * gv[4 * q + 1]), bf_hi(xr[2 * q])));
        o[2 * q + 1] = pack_bf16(fmaf(sv[4 * q + 2], silu_half(0.5f * gv[4 * q + 2]), bf_lo(xr[2 * q + 1])), fmaf(sv[4 * q + 3], silu_half(0.5f * gv[4 * q + 3]), bf_hi(xr[2 * q + 1])));
      }
      const int m = lane >> 3, rr = lane & 7;
      const uint32_t ra = rw + (16 * wi + (m & 1) * 8 + rr) * 160 + (m >> 1) * 16;
#pragma unroll
      for (int q = 0; q < 5; q++) stmatrix_x4(ra + 32 * q, o[4 * q], o[4 * q + 1], o[4 * q + 2], o[4 * q + 3]);
    }
    fence_async_smem();
    mbar_arrive(bars + 8 * (B_STGFULL + w));
    TSTAMP(w * 20 + 16);
    if (threadIdx.x == 0) GSTAMP(52);
    if (wi == 1) asm volatile("fence.acq_rel.cluster;" ::: "memory");
    cluster_arrive_relaxed();
    cluster_wait();
    TDUMP();
  }
}

typedef CUresult (*EncodeFn)(CUtensorMap*, CUtensorMapDataType, cuuint32_t, void*, const cuuint64_t*, const cuuint64_t*, const cuuint32_t*, const cuuint32_t*,
                             CUtensorMapInterleave, CUtensorMapSwizzle, CUtensorMapL2promotion, CUtensorMapFloatOOBfill);

bool encode(EncodeFn fn, CUtensorMap* m, const void* ptr, int rank, const cuuint64_t* dims, const cuuint64_t* strides, const cuuint32_t* box, CUtensorMapSwizzle sw) {
  cuuint32_t es[5] = {1, 1, 1, 1, 1};
  return fn(m, CU_TENSOR_MAP_DATA_TYPE_BFLOAT16, rank, const_cast<void*>(ptr), dims, strides, box, es, CU_TENSOR_MAP_INTERLEAVE_NONE, sw,
            CU_TENSOR_MAP_L2_PROMOTION_L2_128B, CU_TENSOR_MAP_FLOAT_OOB_FILL_NONE) == CUDA_SUCCESS;
}
bool encode2(EncodeFn fn, CUtensorMap* m, const void* ptr, uint64_t cols, uint64_t rows, uint32_t bc, uint32_t br, CUtensorMapSwizzle sw) {
  cuuint64_t dims[2] = {cols, rows}, st[1] = {cols * 2};
  cuuint32_t box[2] = {bc, br};
  return encode(fn, m, ptr, 2, dims, st, box, sw);
}

}

extern "C" void kernel_launch(void* const* d_in, const int* in_sizes, int n_in, void* d_out, int out_size) {
  const __nv_bfloat16* x = (const __nv_bfloat16*)d_in[0];
  const __nv_bfloat16* wqkv = (const __nv_bfloat16*)d_in[1];
  const __nv_bfloat16* wphi = (const __nv_bfloat16*)d_in[2];
  const __nv_bfloat16* wo = (const __nv_bfloat16*)d_in[3];
  const __nv_bfloat16* w1 = (const __nv_bfloat16*)d_in[5];
  const __nv_bfloat16* w2 = (const __nv_bfloat16*)d_in[6];
  static EncodeFn fn = nullptr;
  static Scratch* scr = nullptr;
  if (!fn) {
    void* p = nullptr;
    cudaDriverEntryPointQueryResult q;
    cudaGetDriverEntryPoint("cuTensorMapEncodeTiled", &p, cudaEnableDefault, &q);
    fn = (EncodeFn)p;
    void* ps = nullptr;
    cudaGetSymbolAddress(&ps, g_scr);
    scr = (Scratch*)ps;
    cudaFuncSetAttribute(fused_kernel, cudaFuncAttributeMaxDynamicSharedMemorySize, SMEM_BYTES);
  }
  void *p_wp = scr->wp, *p_h = scr->h, *p_o = scr->o;
  Maps m;
  bool ok = true;
  ok &= encode2(fn, &m.raw, wqkv, 1920, 640, 160, 64, CU_TENSOR_MAP_SWIZZLE_NONE);
  ok &= encode2(fn, &m.w1, w1, 1536, 640, 64, 64, CU_TENSOR_MAP_SWIZZLE_128B);
  ok &= encode2(fn, &m.x, x, 640, 2048, 64, 64, CU_TENSOR_MAP_SWIZZLE_128B);
  ok &= encode2(fn, &m.wp, p_wp, 640, 1920, 64, 80, CU_TENSOR_MAP_SWIZZLE_128B);
  ok &= encode2(fn, &m.h_st, p_h, 1536, 2048, 64, 64, CU_TENSOR_MAP_SWIZZLE_128B);
  ok &= encode2(fn, &m.h_ld, p_h, 1536, 2048, 64, 128, CU_TENSOR_MAP_SWIZZLE_128B);
  ok &= encode2(fn, &m.o_st, p_o, 640, 2048, 80, 64, CU_TENSOR_MAP_SWIZZLE_NONE);
  ok &= encode2(fn, &m.o_ld, p_o, 640, 2048, 64, 128, CU_TENSOR_MAP_SWIZZLE_128B);
  {
    cuuint64_t dims[3] = {32, 1536, 20}, st[2] = {1280, 64};
    cuuint32_t box[3] = {32, 32, 5};
    ok &= encode(fn, &m.w2, w2, 3, dims, st, box, CU_TENSOR_MAP_SWIZZLE_64B);
    dims[1] = 640; box[2] = 3;
    ok &= encode(fn, &m.wo, wo, 3, dims, st, box, CU_TENSOR_MAP_SWIZZLE_64B);
  }
  ok &= encode2(fn, &m.xres, x, 640, 2048, 80, 64, CU_TENSOR_MAP_SWIZZLE_NONE);
  ok &= encode2(fn, &m.out_st, d_out, 640, 2048, 80, 64, CU_TENSOR_MAP_SWIZZLE_NONE);
  if (!ok) return;
  fused_kernel<<<NCTA, NTHREADS, SMEM_BYTES, cudaStreamPerThread>>>(m, x, wphi, wqkv, w1, w2, wo, scr);
}
```
